```python
import torch

def _softmax(x, axis=-1):
    return torch.softmax(x, dim=axis)
def _gelu(x):
    return torch.nn.functional.gelu(x, approximate="tanh")
def _silu(x):
    return torch.nn.functional.silu(x)
def _sigmoid(x):
    return torch.sigmoid(x)
def _layernorm(x, axis=-1, eps=1e-5):
    m = x.mean(dim=axis, keepdim=True)
    v = x.var(dim=axis, keepdim=True, unbiased=False)
    return (x - m) / torch.sqrt(v + eps)
def _scatter_add(tgt, idx, src, axis=0):
    return tgt.clone().index_add_(axis, idx, src)
def _segment_sum(src, seg, n):
    out = torch.zeros((n,) + src.shape[1:], dtype=src.dtype)
    return out.index_add_(0, seg, src)
def _pad(x, pw):
    flat = tuple(v for pair in reversed(pw) for v in pair)
    return torch.nn.functional.pad(x, flat)

kernel_name = 'gated_mix__mha_block_cached__dense_activation_silu__decode'

def setup_inputs():

    _w = (lambda a: (lambda t: t.to(torch.bfloat16) if t.is_floating_point() else t)(torch.as_tensor(a)))
    def _A_setup():
        B, Sq, D = 8, 1, 576
        H, Sk, Dh = 32, 4096, 128
        return {
            "x": _w((lambda *s: torch.randn(*s, dtype=torch.bfloat16) * 0.1)(B, Sq, D)),
            "k_cache": _w((lambda *s: torch.randn(*s, dtype=torch.bfloat16) * 3.2)(B, H, Sk, Dh)),
            "v_cache": _w((lambda *s: torch.randn(*s, dtype=torch.bfloat16) * 3.2)(B, H, Sk, Dh)),
            "wq": _w((lambda *s: torch.randn(*s, dtype=torch.bfloat16) * 3.2)(D, H * Dh) * (D ** -0.5)),
            "wo": _w((lambda *s: torch.randn(*s, dtype=torch.bfloat16) * 3.2)(H * Dh, D) * ((H * Dh) ** -0.5)),
        }
    _A_in = _A_setup()

    def _B_setup():
        B, S, D, F = 8, 1, 576, 4608
        return {
            "x": _w((lambda *s: torch.randn(*s, dtype=torch.bfloat16) * 0.1)(B, S, D)),
            "w1": _w((lambda *s: torch.randn(*s, dtype=torch.bfloat16) * 3.2)(D, F) * (D ** -0.5)),
            "w2": _w((lambda *s: torch.randn(*s, dtype=torch.bfloat16) * 3.2)(F, D) * (F ** -0.5)),
        }
    _B_in = _B_setup()

    return {
        "A_x": _A_in["x"],
        "A_k_cache": _A_in["k_cache"],
        "A_v_cache": _A_in["v_cache"],
        "A_wq": _A_in["wq"],
        "A_wo": _A_in["wo"],
        "B_x": _B_in["x"],
        "B_w1": _B_in["w1"],
        "B_w2": _B_in["w2"],
        "gate_w": _w((lambda *s: torch.randn(*s, dtype=torch.bfloat16) * 0.1)(576) * 16.0),
    }

def reference(A_x, A_k_cache, A_v_cache, A_wq, A_wo, B_x, B_w1, B_w2, gate_w):
    def _A_ref(x, k_cache, v_cache, wq, wo):
        B, Sq, D = x.shape
        H, Dh = 32, 128
        q = (lambda x, *d: x.permute(*d))((x @ wq).reshape(B, Sq, H, Dh), 0, 2, 1, 3)
        scores = torch.einsum("bhqd,bhkd->bhqk", q, k_cache) * (Dh ** -0.5)
        p = _softmax(scores, axis=-1)
        o = torch.einsum("bhqk,bhkd->bhqd", p, v_cache)
        return (lambda x, *d: x.permute(*d))(o, 0, 2, 1, 3).reshape(B, Sq, H * Dh) @ wo

    def _B_ref(x, w1, w2):
        h = torch.einsum("bsd,df->bsf", x, w1)
        h = _silu(h)
        out = torch.einsum("bsf,fd->bsd", h, w2)
        return out

    x = A_x
    g = _sigmoid((x * gate_w).sum(-1, keepdims=True))
    a = _A_ref(x, A_k_cache, A_v_cache, A_wq, A_wo)
    b = _B_ref(x, B_w1, B_w2)
    return g * a + (1 - g) * b
```

```cpp
#include <cuda_runtime.h>
#include <cuda.h>
#include <cuda_bf16.h>
#include <stdint.h>

namespace {

constexpr int NB = 8, DM = 576, NH = 32, SK = 4096, DH = 128, FF = 4608;
constexpr int UNIT_KEYS = 64;
constexpr int TILE_BYTES = UNIT_KEYS * DH * 2;
constexpr int UNITS_PER_PAIR = SK / UNIT_KEYS;
constexpr int NUNITS = NB * NH * UNITS_PER_PAIR;
constexpr int NCONS = 4;
constexpr int NAUX = 9;
constexpr int NTHREADS = (NCONS + NAUX + 1) * 32;
constexpr int NROLE = 128;
constexpr int WROW = 304;
#define DEPTH 3
#define W1_AT 4
#define XLAYOUT 2
#define MERGE_LAG 600

constexpr int SM_KV = 0;
constexpr int SM_WA = SM_KV + NCONS * 2 * TILE_BYTES;
constexpr int SM_WB = SM_WA + 128 * WROW;
constexpr int SM_RED = SM_WB + 576 * 80 + 32;
constexpr int SM_ML = SM_RED + 9 * 32 * 16;
constexpr int SM_O = SM_ML + 64;
constexpr int SM_H = SM_O + 8 * 272;
constexpr int SM_F = SM_H + 8 * WROW;
constexpr int SM_GATE = SM_F + 9 * 32 * 16;
constexpr int SM_BAR = SM_GATE + 64;
constexpr int SM_UNIT = SM_BAR + 32 * 8;
constexpr int SM_TOTAL = SM_UNIT + 32;
static_assert(SM_TOTAL <= 232448, "smem");
constexpr int BAR_K = 0, BAR_V = 4, BAR_E = 8, BAR_WQ = 12, BAR_W1 = 15, BAR_W2 = 18, BAR_WO = 21, BAR_TAG = 23,
              BAR_WFREE = 24, BAR_U = 25, BAR_QOWN = 29, NBARS = 30;

__device__ __align__(128) unsigned g_ticket[32];
__device__ uint4 g_q[NB * NH * 32];
__device__ uint2 g_h[NB * FF / 2];
__device__ uint4 g_part[NUNITS * 32];
__device__ uint4 g_xbuf[4 * 288 * 32];
__device__ __forceinline__ void stamp(int) {}

constexpr unsigned SPIN_LIMIT = 1u << 24;

__device__ __forceinline__ void mbar_init(uint32_t bar, uint32_t cnt) {
    asm volatile("mbarrier.init.shared::cta.b64 [%0], %1;" ::"r"(bar), "r"(cnt) : "memory");
}
__device__ __forceinline__ void mbar_expect_tx(uint32_t bar, uint32_t bytes) {
    asm volatile("mbarrier.arrive.expect_tx.shared::cta.b64 _, [%0], %1;" ::"r"(bar), "r"(bytes) : "memory");
}
__device__ __forceinline__ void mbar_arrive(uint32_t bar) {
    asm volatile("mbarrier.arrive.shared::cta.b64 _, [%0];" ::"r"(bar) : "memory");
}
__device__ __forceinline__ void mbar_wait(uint32_t bar, uint32_t parity) {
    unsigned it = 0;
    while (true) {
        uint32_t ok;
        asm volatile("{\n.reg .pred p;\nmbarrier.try_wait.parity.shared::cta.b64 p, [%1], %2;\nselp.u32 %0, 1, 0, p;\n}"
                     : "=r"(ok) : "r"(bar), "r"(parity) : "memory");
        if (ok) break;
        if (++it > SPIN_LIMIT) __trap();
    }
}
__device__ __forceinline__ void bulk_load_ef(uint32_t dst, const void* src, uint32_t bytes, uint32_t bar, uint64_t pol) {
    asm volatile("cp.async.bulk.shared::cluster.global.mbarrier::complete_tx::bytes.L2::cache_hint [%0], [%1], %2, [%3], %4;"
                 ::"r"(dst), "l"(src), "r"(bytes), "r"(bar), "l"(pol) : "memory");
}
__device__ __forceinline__ void tma_load2d(uint32_t dst, const CUtensorMap* tm, int c0, int c1, uint32_t bar) {
    asm volatile("cp.async.bulk.tensor.2d.shared::cluster.global.mbarrier::complete_tx::bytes [%0], [%1, {%3, %4}], [%2];"
                 ::"r"(dst), "l"(tm), "r"(bar), "r"(c0), "r"(c1) : "memory");
}
__device__ __forceinline__ void named_sync(int id, int n) {
    asm volatile("bar.sync %0, %1;" ::"r"(id), "r"(n) : "memory");
}
__device__ __forceinline__ void lds128(uint32_t (&r)[4], uint32_t addr) {
    asm volatile("ld.shared.v4.u32 {%0,%1,%2,%3}, [%4];" : "=r"(r[0]), "=r"(r[1]), "=r"(r[2]), "=r"(r[3]) : "r"(addr));
}
__device__ __forceinline__ uint32_t lds32(uint32_t addr) {
    uint32_t r; asm volatile("ld.shared.u32 %0, [%1];" : "=r"(r) : "r"(addr)); return r;
}
__device__ __forceinline__ void sts32(uint32_t addr, uint32_t v) {
    asm volatile("st.shared.u32 [%0], %1;" ::"r"(addr), "r"(v) : "memory");
}
__device__ __forceinline__ void ldsm4t(uint32_t (&r)[4], uint32_t addr) {
    asm volatile("ldmatrix.sync.aligned.m8n8.x4.trans.shared.b16 {%0,%1,%2,%3}, [%4];"
                 : "=r"(r[0]), "=r"(r[1]), "=r"(r[2]), "=r"(r[3]) : "r"(addr));
}
__device__ __forceinline__ void mma16816(float (&c)[4], uint32_t a0, uint32_t a1, uint32_t a2, uint32_t a3,
                                         uint32_t b0, uint32_t b1) {
    asm("mma.sync.aligned.m16n8k16.row.col.f32.bf16.bf16.f32 {%0,%1,%2,%3}, {%4,%5,%6,%7}, {%8,%9}, {%0,%1,%2,%3};"
        : "+f"(c[0]), "+f"(c[1]), "+f"(c[2]), "+f"(c[3])
        : "r"(a0), "r"(a1), "r"(a2), "r"(a3), "r"(b0), "r"(b1));
}
__device__ __forceinline__ uint4 ld_b128(const void* p) {
    unsigned long long lo, hi;
    asm volatile("{\n.reg .b128 v;\nld.relaxed.gpu.global.b128 v, [%2];\nmov.b128 {%0, %1}, v;\n}"
                 : "=l"(lo), "=l"(hi) : "l"(p) : "memory");
    return make_uint4((unsigned)lo, (unsigned)(lo >> 32), (unsigned)hi, (unsigned)(hi >> 32));
}
__device__ __forceinline__ void st_b128(void* p, uint4 v) {
    const unsigned long long lo = v.x | ((unsigned long long)v.y << 32), hi = v.z | ((unsigned long long)v.w << 32);
    asm volatile("{\n.reg .b128 v;\nmov.b128 v, {%1, %2};\nst.relaxed.gpu.global.b128 [%0], v;\n}"
                 ::"l"(p), "l"(lo), "l"(hi) : "memory");
}
__device__ __forceinline__ uint4 ld_2x64(const void* p) {
    unsigned long long lo, hi;
    asm volatile("ld.relaxed.gpu.global.v2.b64 {%0, %1}, [%2];" : "=l"(lo), "=l"(hi) : "l"(p) : "memory");
    return make_uint4((unsigned)lo, (unsigned)(lo >> 32), (unsigned)hi, (unsigned)(hi >> 32));
}
__device__ __forceinline__ void st_2x64(void* p, uint4 v) {
    const unsigned long long lo = v.x | ((unsigned long long)v.y << 32), hi = v.z | ((unsigned long long)v.w << 32);
    asm volatile("st.relaxed.gpu.global.v2.b64 [%0], {%1, %2};" ::"l"(p), "l"(lo), "l"(hi) : "memory");
}
__device__ __forceinline__ void st_64(void* p, uint2 v) {
    const unsigned long long w = v.x | ((unsigned long long)v.y << 32);
    asm volatile("st.relaxed.gpu.global.b64 [%0], %1;" ::"l"(p), "l"(w) : "memory");
}
__device__ __forceinline__ unsigned ld_relaxed32(const unsigned* p) {
    unsigned v; asm volatile("ld.relaxed.gpu.global.u32 %0, [%1];" : "=r"(v) : "l"(p) : "memory"); return v;
}
__device__ __forceinline__ unsigned draw_ticket() {
    unsigned v; asm volatile("atom.relaxed.gpu.global.add.u32 %0, [%1], 1;" : "=r"(v) : "l"(&g_ticket[0]) : "memory"); return v;
}
__device__ __forceinline__ uint32_t pack_bf16(float lo, float hi) {
    uint32_t r; asm("cvt.rn.bf16x2.f32 %0, %1, %2;" : "=r"(r) : "f"(hi), "f"(lo)); return r;
}
__device__ __forceinline__ float bf_lo(uint32_t v) { return __uint_as_float(v << 16); }
__device__ __forceinline__ float bf_hi(uint32_t v) { return __uint_as_float(v & 0xffff0000u); }
__device__ __forceinline__ float round_bf16(float v) { return __bfloat162float(__float2bfloat16_rn(v)); }
__device__ __forceinline__ float ex2(float v) { float r; asm("ex2.approx.ftz.f32 %0, %1;" : "=f"(r) : "f"(v)); return r; }
__device__ __forceinline__ float lg2(float v) { float r; asm("lg2.approx.ftz.f32 %0, %1;" : "=f"(r) : "f"(v)); return r; }

__global__ void __launch_bounds__(NTHREADS, 1)
fused_decode_kernel(const __grid_constant__ CUtensorMap tm_wq, const __grid_constant__ CUtensorMap tm_w1,
                    const __grid_constant__ CUtensorMap tm_w2, const __grid_constant__ CUtensorMap tm_wo,
                    const __nv_bfloat16* __restrict__ x, const __nv_bfloat16* __restrict__ kc,
                    const __nv_bfloat16* __restrict__ vc, const __nv_bfloat16* __restrict__ gate_w,
                    __nv_bfloat16* __restrict__ out) {
    extern __shared__ __align__(1024) unsigned char smem[];
    const uint32_t sb = (uint32_t)__cvta_generic_to_shared(smem);
    const int tid = threadIdx.x, warp = tid >> 5, lane = tid & 31;
    const int g = lane >> 2, t = lane & 3;
    const int c = blockIdx.x;
    const bool role = c < NROLE;
    const int head = c >> 2, slice = c & 3;
    const uint32_t bars = sb + SM_BAR;

    if (warp == NCONS + NAUX) {
        unsigned tk = 0;
        uint32_t pbar[DEPTH], ppar[DEPTH];
#pragma unroll
        for (int i = 0; i < DEPTH; i++) { pbar[i] = 0; ppar[i] = 0; }
        auto gate = [&](uint32_t bar, uint32_t par) {
            if (pbar[0]) mbar_wait(pbar[0], ppar[0]);
#pragma unroll
            for (int i = 0; i + 1 < DEPTH; i++) { pbar[i] = pbar[i + 1]; ppar[i] = ppar[i + 1]; }
            pbar[DEPTH - 1] = bar; ppar[DEPTH - 1] = par;
        };
        if (lane == 0) {
            stamp(0);
            tk = draw_ticket();
#pragma unroll
            for (int i = 0; i < NBARS; i++) mbar_init(bars + i * 8, 1);
            asm volatile("fence.mbarrier_init.release.cluster;" ::: "memory");
            asm volatile("fence.proxy.async.shared::cta;" ::: "memory");
            if (role) {
#pragma unroll
                for (int i = 0; i < 3; i++) {
                    mbar_expect_tx(bars + (BAR_WQ + i) * 8, 192 * 64);
                    tma_load2d(sb + SM_WA + i * 192 * 64, &tm_wq, c * 32, i * 192, bars + (BAR_WQ + i) * 8);
                }
            }
        }
        __syncthreads();
        if (lane != 0) return;
        if (role) {
#pragma unroll
            for (int i = (DEPTH > 3 ? 0 : 4 - DEPTH); i < 3; i++) gate(bars + (BAR_WQ + i) * 8, 0);
        }
        const char* kbase = reinterpret_cast<const char*>(kc);
        const char* vbase = reinterpret_cast<const char*>(vc);
        uint64_t pol;
        asm volatile("createpolicy.fractional.L2::evict_first.b64 %0, 1.0;" : "=l"(pol));
        unsigned cur = c, k = 0;
        while (true) {
            const uint32_t st = k % NCONS, par = (k / NCONS) & 1;
            const uint32_t kbar = bars + (BAR_K + st) * 8, vbar = bars + (BAR_V + st) * 8;
            const uint32_t kbuf = sb + SM_KV + st * 2 * TILE_BYTES;
            gate(kbar, par);
            mbar_wait(bars + (BAR_E + st) * 8, par ^ 1);
            mbar_expect_tx(kbar, TILE_BYTES);
            bulk_load_ef(kbuf, kbase + (size_t)cur * TILE_BYTES, TILE_BYTES, kbar, pol);
            sts32(sb + SM_UNIT + st * 4, cur);
            mbar_arrive(bars + (BAR_U + st) * 8);
            if (k == 0) {
                sts32(sb + SM_UNIT + 16, tk / NUNITS + 1);
                mbar_arrive(bars + BAR_TAG * 8);
                if (role) {
                    asm volatile("prefetch.tensormap [%0];" ::"l"(&tm_w1) : "memory");
                    asm volatile("prefetch.tensormap [%0];" ::"l"(&tm_w2) : "memory");
                    asm volatile("prefetch.tensormap [%0];" ::"l"(&tm_wo) : "memory");
                }
            } else {
                tk = draw_ticket();
            }
            gate(vbar, par);
            mbar_expect_tx(vbar, TILE_BYTES);
            bulk_load_ef(kbuf + TILE_BYTES, vbase + (size_t)cur * TILE_BYTES, TILE_BYTES, vbar, pol);
            k++;
            cur = (tk & (NUNITS - 1)) + gridDim.x;
            if (role && (k == W1_AT || (cur >= (unsigned)NUNITS && k < W1_AT))) {
#pragma unroll
                for (int i = 0; i < 3; i++) {
                    gate(bars + (BAR_W1 + i) * 8, 0);
                    mbar_expect_tx(bars + (BAR_W1 + i) * 8, 192 * 80);
                    tma_load2d(sb + SM_WB + i * 192 * 80, &tm_w1, c * 36 - (c & 1) * 4, i * 192, bars + (BAR_W1 + i) * 8);
                }
            }
            if (cur >= (unsigned)NUNITS) break;
        }
        stamp(8);
        if (role) {
            mbar_wait(bars + BAR_WFREE * 8, 0);
            asm volatile("fence.proxy.async.shared::cta;" ::: "memory");
#pragma unroll
            for (int i = 0; i < 3; i++) {
                gate(bars + (BAR_W2 + i) * 8, 0);
                mbar_expect_tx(bars + (BAR_W2 + i) * 8, 48 * WROW);
                tma_load2d(sb + SM_WB + i * 48 * WROW, &tm_w2, slice * 144, head * 144 + i * 48, bars + (BAR_W2 + i) * 8);
            }
#pragma unroll
            for (int i = 0; i < 2; i++) {
                gate(bars + (BAR_WO + i) * 8, 0);
                mbar_expect_tx(bars + (BAR_WO + i) * 8, 64 * WROW);
                tma_load2d(sb + SM_WA + i * 64 * WROW, &tm_wo, slice * 144, head * 128 + i * 64, bars + (BAR_WO + i) * 8);
            }
        }
        stamp(15);
        for (int i = 0; i < NCONS; i++, k++) {
            const uint32_t st = k % NCONS, par = (k / NCONS) & 1;
            mbar_wait(bars + (BAR_E + st) * 8, par ^ 1);
            sts32(sb + SM_UNIT + st * 4, 0xffffffffu);
            mbar_arrive(bars + (BAR_U + st) * 8);
        }
    } else if (warp < NCONS) {
        const uint32_t kbuf = sb + SM_KV + warp * 2 * TILE_BYTES, vbuf = kbuf + TILE_BYTES;
        const uint32_t kbar = bars + (BAR_K + warp) * 8, vbar = bars + (BAR_V + warp) * 8;
        const uint32_t par = g & 1;
        const uint32_t ka0 = kbuf + g * 256 + 64 * (0 ^ par) + 16 * t;
        const uint32_t ka1 = kbuf + g * 256 + 64 * (1 ^ par) + 16 * t;
        const uint32_t vrow = vbuf + ((lane & 7) + 8 * (lane >> 4)) * 256;
        const uint32_t xr16 = (((lane >> 3) & 1) ^ (lane & 7)) * 16;
        uint32_t va[4];
#pragma unroll
        for (int j = 0; j < 4; j++) va[j] = vrow + ((32 * j) ^ xr16);
        const uint32_t qoff0 = 8 * (0 ^ par) + 2 * t, qoff1 = 8 * (1 ^ par) + 2 * t;
        const bool pown = (t == (g >> 1));
        const float sc = 0.08838834764831845f * 1.4426950408889634f;
        __syncthreads();
        unsigned tag = 0;
        uint32_t live = 0;
        for (uint32_t ph = 1;; ph ^= 1) {
            asm volatile("" : "+r"(live));
            unsigned u = 0;
            uint4 qr[8];
#pragma unroll
            for (int i = 0; i < 8; i++) qr[i] = make_uint4(0, 0, 0, 0);
            if (live) {
                mbar_wait(bars + (BAR_U + warp) * 8, ph);
                u = lds32(sb + SM_UNIT + warp * 4);
                if (u == 0xffffffffu) break;
                const uint4* qp = g_q + (u / UNITS_PER_PAIR) * 32;
                unsigned it = 0;
                while (true) {
                    qr[0] = ld_2x64(qp + qoff0);      qr[1] = ld_2x64(qp + qoff0 + 1);
                    qr[2] = ld_2x64(qp + qoff1);      qr[3] = ld_2x64(qp + qoff1 + 1);
                    qr[4] = ld_2x64(qp + qoff0 + 16); qr[5] = ld_2x64(qp + qoff0 + 17);
                    qr[6] = ld_2x64(qp + qoff1 + 16); qr[7] = ld_2x64(qp + qoff1 + 17);
                    unsigned bad = 0;
#pragma unroll
                    for (int i = 0; i < 8; i++) bad |= (qr[i].y ^ tag) | (qr[i].w ^ tag);
                    if (!__any_sync(0xffffffffu, bad != 0)) break;
                    if (++it > SPIN_LIMIT) __trap();
                    __nanosleep(200);
                }
                mbar_wait(kbar, ph);
            }
            float s[4][2];
#pragma unroll
            for (int kb = 0; kb < 4; kb++) {
                float acc[4] = {0.f, 0.f, 0.f, 0.f};
#pragma unroll
                for (int i = 0; i < 4; i++) {
                    uint32_t r0[4], r1[4];
                    const uint32_t a = ((i & 1) ? ka1 : ka0) + (i >> 1) * 128 + kb * 4096;
                    lds128(r0, a);
                    lds128(r1, a + 2048);
                    mma16816(acc, r0[0], r1[0], r0[1], r1[1], qr[2 * i].x, qr[2 * i].z);
                    mma16816(acc, r0[2], r1[2], r0[3], r1[3], qr[2 * i + 1].x, qr[2 * i + 1].z);
                }
                s[kb][0] = par ? acc[1] : acc[0];
                s[kb][1] = par ? acc[3] : acc[2];
            }
            float m = fmaxf(fmaxf(fmaxf(s[0][0], s[0][1]), fmaxf(s[1][0], s[1][1])),
                            fmaxf(fmaxf(s[2][0], s[2][1]), fmaxf(s[3][0], s[3][1])));
            m = fmaxf(m, __shfl_xor_sync(0xffffffffu, m, 4));
            m = fmaxf(m, __shfl_xor_sync(0xffffffffu, m, 8));
            m = fmaxf(m, __shfl_xor_sync(0xffffffffu, m, 16));
            const float ms = m * sc;
            float l = 0.f;
            uint32_t pb[4][2];
#pragma unroll
            for (int kb = 0; kb < 4; kb++) {
#pragma unroll
                for (int hh = 0; hh < 2; hh++) {
                    const float p = ex2(fmaf(s[kb][hh], sc, -ms));
                    l += p;
                    const uint32_t pk = par ? pack_bf16(0.f, p) : pack_bf16(p, 0.f);
                    pb[kb][hh] = pown ? pk : 0u;
                }
            }
            l += __shfl_xor_sync(0xffffffffu, l, 4);
            l += __shfl_xor_sync(0xffffffffu, l, 8);
            l += __shfl_xor_sync(0xffffffffu, l, 16);
            const float rl = 1.0f / l;
            const float lse = ms + lg2(l);
            if (live) mbar_wait(vbar, ph);
            float o[8][4];
#pragma unroll
            for (int j = 0; j < 8; j++) { o[j][0] = o[j][1] = o[j][2] = o[j][3] = 0.f; }
#pragma unroll
            for (int kb = 0; kb < 4; kb++) {
#pragma unroll
                for (int j = 0; j < 8; j++) {
                    uint32_t a[4];
                    ldsm4t(a, va[j & 3] + (j >> 2) * 128 + kb * 4096);
                    mma16816(o[j], a[0], a[1], a[2], a[3], pb[kb][0], pb[kb][1]);
                }
            }
            float e[8][2];
#pragma unroll
            for (int j = 0; j < 8; j++) { e[j][0] = o[j][0] + o[j][3]; e[j][1] = o[j][1] + o[j][2]; }
#pragma unroll
            for (int j = 0; j < 8; j += 2) {
                e[j][0] += __shfl_xor_sync(0xffffffffu, e[j + 1][0], 1);
                e[j][1] += __shfl_xor_sync(0xffffffffu, e[j + 1][1], 1);
            }
#pragma unroll
            for (int j = 0; j < 8; j += 4) {
                e[j][0] += __shfl_xor_sync(0xffffffffu, e[j + 2][0], 2);
                e[j][1] += __shfl_xor_sync(0xffffffffu, e[j + 2][1], 2);
            }
            const uint4 pv = make_uint4(pack_bf16(e[0][0] * rl, e[0][1] * rl), pack_bf16(e[4][0] * rl, e[4][1] * rl),
                                        __float_as_uint(lse), tag);
            if (live) {
                st_b128(&g_part[(size_t)u * 32 + lane], pv);
                __syncwarp();
                if (lane == 0) mbar_arrive(bars + (BAR_E + warp) * 8);
            } else {
                asm volatile("" ::"r"(pv.x), "r"(pv.y), "r"(pv.z));
                mbar_wait(bars + BAR_TAG * 8, 0);
                tag = lds32(sb + SM_UNIT + 16);
                if (role) mbar_wait(bars + BAR_QOWN * 8, 0); else __nanosleep(3000);
                live = 1;
            }
        }
    } else {
        const int a = warp - NCONS, at = tid - NCONS * 32;
        uint32_t xq[9][2];
        if (role && a < 8) {
            const uint32_t* xp = reinterpret_cast<const uint32_t*>(x + g * DM + (a >> 1) * 144 + 2 * t);
#pragma unroll
            for (int i = 0; i < 9; i++) { xq[i][0] = __ldg(xp + i * 8); xq[i][1] = __ldg(xp + i * 8 + 4); }
        }
        __syncthreads();
        if (!role) return;
        unsigned tag = 0;
#pragma unroll 1
        for (uint32_t live = 0; live < 2; live++) {
            asm volatile("" : "+r"(live));
            if (a < 8) {
                if (live) {
                    mbar_wait(bars + (BAR_WQ + 0) * 8, 0);
                    mbar_wait(bars + (BAR_WQ + 1) * 8, 0);
                    mbar_wait(bars + (BAR_WQ + 2) * 8, 0);
                    if (at == 0) stamp(14);
                }
                float acc[4] = {0.f, 0.f, 0.f, 0.f}, acb[4] = {0.f, 0.f, 0.f, 0.f};
                const int mt = a & 1;
#pragma unroll
                for (int i = 0; i < 9; i++) {
                    const int row = (a >> 1) * 144 + i * 16 + (lane & 7) + 8 * (lane >> 4);
                    const int ch = mt * 2 + ((lane >> 3) & 1);
                    uint32_t w[4];
                    ldsm4t(w, sb + SM_WA + row * 64 + ((ch ^ ((row >> 1) & 3)) << 4));
                    if (i & 1) mma16816(acb, w[0], w[1], w[2], w[3], xq[i][0], xq[i][1]);
                    else mma16816(acc, w[0], w[1], w[2], w[3], xq[i][0], xq[i][1]);
                }
                *reinterpret_cast<float4*>(smem + SM_RED + (a * 32 + lane) * 16) =
                    make_float4(acc[0] + acb[0], acc[1] + acb[1], acc[2] + acb[2], acc[3] + acb[3]);
            }
            named_sync(1, 288);
            if (at < 128) {
                const int b = at >> 4, cp = at & 15;
                const int mt = cp >> 3, r = (2 * cp) & 15;
                const float* rp = reinterpret_cast<const float*>(smem + SM_RED) +
                                  (mt * 32 + (r & 7) * 4 + (b >> 1)) * 4 + (r >> 3) * 2 + (b & 1);
                const float v0 = rp[0] + rp[256] + rp[512] + rp[768];
                const float v1 = rp[16] + rp[272] + rp[528] + rp[784];
                const uint32_t qword = pack_bf16(v0, v1);
                if (live) st_64(reinterpret_cast<uint2*>(g_q + (b * NH + head) * 32) + slice * 16 + cp, make_uint2(qword, tag));
                else asm volatile("" ::"r"(qword));
            }
            if (!live) {
                mbar_wait(bars + BAR_TAG * 8, 0);
                tag = lds32(sb + SM_UNIT + 16);
                named_sync(1, 288);
            }
        }
        if (at == 0) { mbar_arrive(bars + BAR_QOWN * 8); stamp(6); }

        {
            const int mt = a % 3, kt = a / 3;
            uint32_t xh[12][2];
            const uint32_t* xp = reinterpret_cast<const uint32_t*>(x + g * DM + kt * 192 + 2 * t);
#pragma unroll
            for (int i = 0; i < 12; i++) { xh[i][0] = __ldg(xp + i * 8); xh[i][1] = __ldg(xp + i * 8 + 4); }
            mbar_wait(bars + (BAR_W1 + 0) * 8, 0);
            mbar_wait(bars + (BAR_W1 + 1) * 8, 0);
            mbar_wait(bars + (BAR_W1 + 2) * 8, 0);
            float acc[4] = {0.f, 0.f, 0.f, 0.f};
#pragma unroll
            for (int i = 0; i < 12; i++) {
                const int row = kt * 192 + i * 16 + (lane & 7) + 8 * (lane >> 4);
                uint32_t w[4];
                ldsm4t(w, sb + SM_WB + row * 80 + (mt * 2 + ((lane >> 3) & 1)) * 16);
                mma16816(acc, w[0], w[1], w[2], w[3], xh[i][0], xh[i][1]);
            }
            named_sync(1, 288);
            *reinterpret_cast<float4*>(smem + SM_RED + (a * 32 + lane) * 16) = make_float4(acc[0], acc[1], acc[2], acc[3]);
            named_sync(1, 288);
            if (at == 287) mbar_arrive(bars + BAR_WFREE * 8);
            if (at < 144) {
                const int b = at / 18, cp = at - b * 18;
                const int sc2 = 2 * cp + (c & 1) * 4;
                const int m2 = sc2 >> 4, r = sc2 & 15;
                const float* rp = reinterpret_cast<const float*>(smem + SM_RED) +
                                  (m2 * 32 + (r & 7) * 4 + (b >> 1)) * 4 + (r >> 3) * 2 + (b & 1);
                const float v0 = round_bf16(rp[0] + rp[384] + rp[768]);
                const float v1 = round_bf16(rp[16] + rp[400] + rp[784]);
                st_64(g_h + b * (FF / 2) + c * 18 + cp,
                      make_uint2(pack_bf16(v0 / (1.0f + __expf(-v0)), v1 / (1.0f + __expf(-v1))), tag));
            }
        }

        if (a == 8) {
            for (int b = 0; b < NB; b++) {
                float sum = 0.f;
#pragma unroll
                for (int i = 0; i < 9; i++) {
                    const uint32_t xv = __ldg(reinterpret_cast<const uint32_t*>(x + b * DM) + lane + i * 32);
                    const uint32_t gv = __ldg(reinterpret_cast<const uint32_t*>(gate_w) + lane + i * 32);
                    sum += round_bf16(bf_lo(xv) * bf_lo(gv)) + round_bf16(bf_hi(xv) * bf_hi(gv));
                }
#pragma unroll
                for (int o2 = 16; o2 > 0; o2 >>= 1) sum += __shfl_xor_sync(0xffffffffu, sum, o2);
                const float z = round_bf16(sum);
                const float gt = round_bf16(1.0f / (1.0f + __expf(-z)));
                if (lane == 0) {
                    reinterpret_cast<float*>(smem + SM_GATE)[b] = gt;
                    reinterpret_cast<float*>(smem + SM_GATE)[8 + b] = round_bf16(1.0f - gt);
                }
            }
            __nanosleep(4000);
            for (int i = lane; i < 288; i += 32) {
                const int b = i / 36, ch = i - b * 36;
                const uint2* src = g_h + b * (FF / 2) + head * 72 + ch * 2;
                uint4 v;
                unsigned it = 0;
                while (true) {
                    v = ld_2x64(src);
                    if (v.y == tag && v.w == tag) break;
                    if (++it > SPIN_LIMIT) __trap();
                    __nanosleep(200);
                }
                *reinterpret_cast<uint2*>(smem + SM_H + b * WROW + ch * 8) = make_uint2(v.x, v.z);
            }
            __syncwarp();
        }

#pragma unroll 1
        for (uint32_t live = 0; live < 2; live++) {
            asm volatile("" : "+r"(live));
            if (a == 8) {
                const float n0 = reinterpret_cast<const float*>(smem + SM_GATE)[8 + 2 * t];
                const float n1 = reinterpret_cast<const float*>(smem + SM_GATE)[9 + 2 * t];
                float fa[9][4];
#pragma unroll
                for (int m = 0; m < 9; m++) { fa[m][0] = fa[m][1] = fa[m][2] = fa[m][3] = 0.f; }
                const uint32_t wsel = sb + SM_WB + ((lane & 7) + 8 * (lane >> 4)) * WROW + ((lane >> 3) & 1) * 16;
#pragma unroll 1
                for (int i3 = 0; i3 < 3; i3++) {
                    uint32_t hb[3][2];
#pragma unroll
                    for (int i = 0; i < 3; i++) {
                        hb[i][0] = lds32(sb + SM_H + g * WROW + (i3 * 3 + i) * 32 + t * 4);
                        hb[i][1] = lds32(sb + SM_H + g * WROW + (i3 * 3 + i) * 32 + t * 4 + 16);
                    }
                    if (live) mbar_wait(bars + (BAR_W2 + i3) * 8, 0);
#pragma unroll
                    for (int i = 0; i < 3; i++) {
#pragma unroll
                        for (int m = 0; m < 9; m++) {
                            uint32_t w[4];
                            ldsm4t(w, wsel + (i3 * 3 + i) * 16 * WROW + m * 32);
                            mma16816(fa[m], w[0], w[1], w[2], w[3], hb[i][0], hb[i][1]);
                        }
                    }
                }
#pragma unroll
                for (int m = 0; m < 9; m++)
                    *reinterpret_cast<float4*>(smem + SM_F + (m * 32 + lane) * 16) =
                        make_float4(n0 * fa[m][0], n1 * fa[m][1], n0 * fa[m][2], n1 * fa[m][3]);
            } else {
#pragma unroll 1
                for (int b = live ? NB - 1 : 0; b < NB - 1 + (int)live; b++) {
                    const int pair = b * NH + head;
                    if (at == 0) {
                        const unsigned base = (tag - 1) * NUNITS;
                        const unsigned need = min((pair + 1) * UNITS_PER_PAIR + MERGE_LAG, NUNITS);
                        unsigned it = 0;
                        while (ld_relaxed32(&g_ticket[0]) - base < need) {
                            __nanosleep(live ? 200 : 1000);
                            if (++it > SPIN_LIMIT) __trap();
                        }
                        if (live) stamp(9);
                    }
                    named_sync(2, 256);
                    uint4 pv[8];
                    const uint4* pp = &g_part[(size_t)(pair * UNITS_PER_PAIR + a * 8) * 32 + lane];
#pragma unroll
                    for (int i = 0; i < 8; i++) pv[i].w = tag + 1;
                    unsigned it = 0;
                    while (true) {
#pragma unroll
                        for (int i = 0; i < 8; i++) if (pv[i].w != tag) pv[i] = ld_b128(pp + i * 32);
                        unsigned bad = 0;
#pragma unroll
                        for (int i = 0; i < 8; i++) bad |= pv[i].w ^ tag;
                        if (bad == 0) break;
                        if (++it > SPIN_LIMIT) __trap();
                    }
                    __syncwarp();
                    float mw = __uint_as_float(pv[0].z);
#pragma unroll
                    for (int i = 1; i < 8; i++) mw = fmaxf(mw, __uint_as_float(pv[i].z));
                    float lw = 0.f, o0 = 0.f, o1 = 0.f, o2 = 0.f, o3 = 0.f;
#pragma unroll
                    for (int i = 0; i < 8; i++) {
                        const float w = ex2(__uint_as_float(pv[i].z) - mw);
                        lw += w;
                        o0 = fmaf(w, bf_lo(pv[i].x), o0); o1 = fmaf(w, bf_hi(pv[i].x), o1);
                        o2 = fmaf(w, bf_lo(pv[i].y), o2); o3 = fmaf(w, bf_hi(pv[i].y), o3);
                    }
                    *reinterpret_cast<float4*>(smem + SM_RED + (a * 32 + lane) * 16) = make_float4(o0, o1, o2, o3);
                    if (lane == 0) *reinterpret_cast<float2*>(smem + SM_ML + a * 8) = make_float2(mw, lw);
                    named_sync(2, 256);
                    if (at < 128) {
                        const int ln = at >> 2, i = at & 3;
                        const float2* ml = reinterpret_cast<const float2*>(smem + SM_ML);
                        float M = ml[0].x;
#pragma unroll
                        for (int w = 1; w < 8; w++) M = fmaxf(M, ml[w].x);
                        float L = 0.f, ov = 0.f;
#pragma unroll
                        for (int w = 0; w < 8; w++) {
                            const float sw = ex2(ml[w].x - M);
                            L = fmaf(sw, ml[w].y, L);
                            ov = fmaf(sw, reinterpret_cast<const float*>(smem + SM_RED)[(w * 32 + ln) * 4 + i], ov);
                        }
                        const int d = (i >> 1) * 64 + 16 * (ln & 3) + 8 * (i & 1) + (ln >> 2);
                        reinterpret_cast<__nv_bfloat16*>(smem + SM_O)[b * 136 + d] = __float2bfloat16_rn(__fdividef(ov, L));
                    }
                }
                if (at == 0) stamp(10);
            }
            named_sync(1, 288);

            float aa[4] = {0.f, 0.f, 0.f, 0.f}, ab[4] = {0.f, 0.f, 0.f, 0.f};
            const uint32_t wsel = sb + SM_WA + ((lane & 7) + 8 * (lane >> 4)) * WROW + (2 * a + ((lane >> 3) & 1)) * 16;
            uint32_t ob[8][2];
#pragma unroll
            for (int i = 0; i < 8; i++) {
                ob[i][0] = lds32(sb + SM_O + g * 272 + i * 32 + t * 4);
                ob[i][1] = lds32(sb + SM_O + g * 272 + i * 32 + t * 4 + 16);
            }
            const float4 f = *reinterpret_cast<const float4*>(smem + SM_F + at * 16);
            const float g0 = reinterpret_cast<const float*>(smem + SM_GATE)[2 * t];
            const float g1 = reinterpret_cast<const float*>(smem + SM_GATE)[2 * t + 1];
#pragma unroll
            for (int i = 0; i < 8; i += 2) {
                if (i % 4 == 0 && live) mbar_wait(bars + (BAR_WO + i / 4) * 8, 0);
                if (i == 4 && at == 0) stamp(11);
                uint32_t w[4], w2[4];
                ldsm4t(w, wsel + i * 16 * WROW);
                ldsm4t(w2, wsel + (i + 1) * 16 * WROW);
                mma16816(aa, w[0], w[1], w[2], w[3], ob[i][0], ob[i][1]);
                mma16816(ab, w2[0], w2[1], w2[2], w2[3], ob[i + 1][0], ob[i + 1][1]);
            }
            const unsigned t2 = tag & 3u, wtag = live ? t2 : (t2 ^ 2u);
            const uint4 y = make_uint4((__float_as_uint(fmaf(g0, aa[0] + ab[0], f.x)) & ~3u) | wtag,
                                       (__float_as_uint(fmaf(g1, aa[1] + ab[1], f.y)) & ~3u) | wtag,
                                       (__float_as_uint(fmaf(g0, aa[2] + ab[2], f.z)) & ~3u) | wtag,
                                       (__float_as_uint(fmaf(g1, aa[3] + ab[3], f.w)) & ~3u) | wtag);
            st_2x64(&g_xbuf[(slice * 32 + head) * 288 + at], y);
            const uint4* src = &g_xbuf[(slice * 32 + at / 9) * 288 + head * 9 + at % 9];
            if (at == 0) stamp(13);
            uint4 ya = make_uint4(t2, t2, t2, t2);
            unsigned it = 0;
            while (true) {
                if (live) ya = ld_2x64(src);
                if ((((ya.x ^ t2) | (ya.y ^ t2) | (ya.z ^ t2) | (ya.w ^ t2)) & 3u) == 0u) break;
                if (++it > SPIN_LIMIT) __trap();
            }
            *reinterpret_cast<uint4*>(smem + SM_RED + ((at % 9) * 32 + at / 9) * 16) = ya;
            named_sync(1, 288);
            ya = *reinterpret_cast<const uint4*>(smem + SM_RED + at * 16);
            __syncwarp();
            float v0 = __uint_as_float(ya.x & ~3u), v1 = __uint_as_float(ya.y & ~3u);
            float v2 = __uint_as_float(ya.z & ~3u), v3 = __uint_as_float(ya.w & ~3u);
            {
                const bool hi = lane & 16;
                const float s0 = hi ? v0 : v2, s1 = hi ? v1 : v3;
                float k0 = (hi ? v2 : v0) + __shfl_xor_sync(0xffffffffu, s0, 16);
                float k1 = (hi ? v3 : v1) + __shfl_xor_sync(0xffffffffu, s1, 16);
                const bool od = lane & 8;
                v0 = (od ? k1 : k0) + __shfl_xor_sync(0xffffffffu, od ? k0 : k1, 8);
                v0 += __shfl_xor_sync(0xffffffffu, v0, 4);
                v0 += __shfl_xor_sync(0xffffffffu, v0, 2);
                v0 += __shfl_xor_sync(0xffffffffu, v0, 1);
            }
            const int wt = head * 9 + a;
            const int col = slice * 144 + (wt >> 5) * 16 + ((wt & 31) >> 2) + 8 * (lane >> 4);
            const int b = 2 * (wt & 3) + ((lane >> 3) & 1);
            const __nv_bfloat16 r = __float2bfloat16_rn(v0);
            if (live && (lane & 7) == 0) out[b * DM + col] = r;
            if (!live) named_sync(1, 288);
            if (at == 0) stamp(12);
        }
    }
}

typedef CUresult (*EncodeTiledFn)(CUtensorMap*, CUtensorMapDataType, cuuint32_t, void*, const cuuint64_t*,
                                  const cuuint64_t*, const cuuint32_t*, const cuuint32_t*, CUtensorMapInterleave,
                                  CUtensorMapSwizzle, CUtensorMapL2promotion, CUtensorMapFloatOOBfill);

void make_map(EncodeTiledFn enc, CUtensorMap* tm, const void* base, int cols, int rows, int bc, int br,
              CUtensorMapSwizzle sw, CUtensorMapL2promotion promo = CU_TENSOR_MAP_L2_PROMOTION_NONE) {
    cuuint64_t dims[2] = {(cuuint64_t)cols, (cuuint64_t)rows};
    cuuint64_t strides[1] = {(cuuint64_t)cols * 2};
    cuuint32_t box[2] = {(cuuint32_t)bc, (cuuint32_t)br};
    cuuint32_t es[2] = {1, 1};
    enc(tm, CU_TENSOR_MAP_DATA_TYPE_BFLOAT16, 2, const_cast<void*>(base), dims, strides, box, es,
        CU_TENSOR_MAP_INTERLEAVE_NONE, sw, promo, CU_TENSOR_MAP_FLOAT_OOB_FILL_NONE);
}

}

extern "C" void kernel_launch(void* const* d_in, const int* in_sizes, int n_in, void* d_out, int out_size) {
    (void)in_sizes; (void)n_in; (void)out_size;
    static int grid = 0;
    static EncodeTiledFn enc = nullptr;
    if (grid == 0) {
        int dev = 0, sms = 0;
        cudaGetDevice(&dev);
        cudaDeviceGetAttribute(&sms, cudaDevAttrMultiProcessorCount, dev);
        cudaFuncSetAttribute(fused_decode_kernel, cudaFuncAttributeMaxDynamicSharedMemorySize, SM_TOTAL);
        void* fn = nullptr;
        cudaDriverEntryPointQueryResult qr;
        cudaGetDriverEntryPoint("cuTensorMapEncodeTiled", &fn, cudaEnableDefault, &qr);
        enc = (EncodeTiledFn)fn;
        grid = sms < NROLE ? NROLE : sms;
    }
    const __nv_bfloat16* x = (const __nv_bfloat16*)d_in[0];
    const __nv_bfloat16* kc = (const __nv_bfloat16*)d_in[1];
    const __nv_bfloat16* vc = (const __nv_bfloat16*)d_in[2];
    const __nv_bfloat16* gw = (const __nv_bfloat16*)d_in[8];
    CUtensorMap tm_wq, tm_w1, tm_w2, tm_wo;
#define PROMO CU_TENSOR_MAP_L2_PROMOTION_NONE
    make_map(enc, &tm_wq, d_in[3], NH * DH, DM, 32, 192, CU_TENSOR_MAP_SWIZZLE_64B, PROMO);
    make_map(enc, &tm_w1, d_in[6], FF, DM, 40, 192, CU_TENSOR_MAP_SWIZZLE_NONE, PROMO);
    make_map(enc, &tm_w2, d_in[7], DM, FF, 152, 48, CU_TENSOR_MAP_SWIZZLE_NONE);
    make_map(enc, &tm_wo, d_in[4], DM, NH * DH, 152, 64, CU_TENSOR_MAP_SWIZZLE_NONE);
    fused_decode_kernel<<<grid, NTHREADS, SM_TOTAL>>>(tm_wq, tm_w1, tm_w2, tm_wo, x, kc, vc, gw, (__nv_bfloat16*)d_out);
}
```

```cpp
#include <cuda_runtime.h>
#include <cuda.h>
#include <cuda_bf16.h>
#include <stdint.h>
#include <math.h>

namespace {

constexpr int NB = 8, DM = 576, NH = 32, SK = 4096, DH = 128, FF = 4608;
constexpr int UNIT_KEYS = 64;
constexpr int TILE_BYTES = UNIT_KEYS * DH * 2;
constexpr int UNITS_PER_PAIR = SK / UNIT_KEYS;
constexpr int NUNITS = NB * NH * UNITS_PER_PAIR;
constexpr int NCONS = 4;
constexpr int NAUX = 9;
constexpr int NTHREADS = (NCONS + NAUX + 1) * 32;
constexpr int NROLE = 128;
constexpr int WROW = 304;
constexpr int W1_AT = NCONS;
constexpr int MERGE_LAG = 600;

constexpr int SM_KV = 0;
constexpr int SM_WA = SM_KV + NCONS * 2 * TILE_BYTES;
constexpr int SM_WB = SM_WA + 128 * WROW;
constexpr int SM_RED = SM_WB + 576 * 80 + 32;
constexpr int SM_ML = SM_RED + 9 * 32 * 16;
constexpr int SM_O = SM_ML + 64;
constexpr int SM_H = SM_O + 8 * 272;
constexpr int SM_F = SM_H + 8 * WROW;
constexpr int SM_X = SM_O;
constexpr int SM_GATE = SM_F + 9 * 32 * 16;
constexpr int SM_BAR = SM_GATE + 64;
constexpr int SM_UNIT = SM_BAR + 32 * 8;
constexpr int SM_TOTAL = SM_UNIT + 32;
static_assert(SM_TOTAL <= 232448 && SM_X + NB * DM * 2 <= SM_GATE && SM_X % 16 == 0, "smem");
constexpr int BAR_K = 0, BAR_V = 4, BAR_E = 8, BAR_U = 12, BAR_WQ = 16, BAR_TAG = 17, BAR_WFREE = 18, BAR_QOWN = 19,
              BAR_W1 = 20, BAR_W2 = 23, BAR_WO = 26, BAR_X = 28, NBARS = 29;

struct __align__(1024) Scratch {
    unsigned ticket[256];
    uint4 q[NB * NH * 32];
    uint4 xbuf[4 * 288 * 32];
    uint2 h[NB * FF / 2];
    uint4 part[NUNITS * 32];
};
__device__ Scratch g_scratch;

constexpr unsigned SPIN_LIMIT = 1u << 22;
constexpr unsigned WAIT_CLKS = 3000000000u;

__device__ __forceinline__ void mbar_init(uint32_t bar, uint32_t cnt) {
    asm volatile("mbarrier.init.shared::cta.b64 [%0], %1;" ::"r"(bar), "r"(cnt) : "memory");
}
__device__ __forceinline__ void mbar_expect_tx(uint32_t bar, uint32_t bytes) {
    asm volatile("mbarrier.arrive.expect_tx.shared::cta.b64 _, [%0], %1;" ::"r"(bar), "r"(bytes) : "memory");
}
__device__ __forceinline__ void mbar_arrive(uint32_t bar) {
    asm volatile("mbarrier.arrive.shared::cta.b64 _, [%0];" ::"r"(bar) : "memory");
}
__device__ __forceinline__ bool mbar_try(uint32_t bar, uint32_t parity) {
    uint32_t ok;
    asm volatile("{\n.reg .pred p;\nmbarrier.try_wait.parity.shared::cta.b64 p, [%1], %2;\nselp.u32 %0, 1, 0, p;\n}"
                 : "=r"(ok) : "r"(bar), "r"(parity) : "memory");
    return ok != 0;
}
__device__ __forceinline__ void mbar_wait(uint32_t bar, uint32_t parity) {
    if (mbar_try(bar, parity)) return;
    const unsigned t0 = (unsigned)clock();
    while (!mbar_try(bar, parity))
        if ((unsigned)clock() - t0 > WAIT_CLKS) __trap();
}
__device__ __forceinline__ void mbar_spin(uint32_t bar, uint32_t parity) {
    for (unsigned it = 0;; it++) {
        uint32_t ok;
        asm volatile("{\n.reg .pred p;\nmbarrier.test_wait.parity.shared::cta.b64 p, [%1], %2;\nselp.u32 %0, 1, 0, p;\n}"
                     : "=r"(ok) : "r"(bar), "r"(parity) : "memory");
        if (ok) break;
        if (it > (1u << 26)) __trap();
    }
}
__device__ __forceinline__ void bulk_load_ef(uint32_t dst, const void* src, uint32_t bytes, uint32_t bar, uint64_t pol) {
    asm volatile("cp.async.bulk.shared::cluster.global.mbarrier::complete_tx::bytes.L2::cache_hint [%0], [%1], %2, [%3], %4;"
                 ::"r"(dst), "l"(src), "r"(bytes), "r"(bar), "l"(pol) : "memory");
}
__device__ __forceinline__ void tma_load2d(uint32_t dst, const CUtensorMap* tm, int c0, int c1, uint32_t bar) {
    asm volatile("cp.async.bulk.tensor.2d.shared::cluster.global.mbarrier::complete_tx::bytes [%0], [%1, {%3, %4}], [%2];"
                 ::"r"(dst), "l"(tm), "r"(bar), "r"(c0), "r"(c1) : "memory");
}
__device__ __forceinline__ void named_sync(int id, int n) {
    asm volatile("bar.sync %0, %1;" ::"r"(id), "r"(n) : "memory");
}
__device__ __forceinline__ uint32_t lds32(uint32_t addr) {
    uint32_t r; asm volatile("ld.shared.u32 %0, [%1];" : "=r"(r) : "r"(addr)); return r;
}
__device__ __forceinline__ void sts32(uint32_t addr, uint32_t v) {
    asm volatile("st.shared.u32 [%0], %1;" ::"r"(addr), "r"(v) : "memory");
}
__device__ __forceinline__ void ldsm4t(uint32_t (&r)[4], uint32_t addr) {
    asm volatile("ldmatrix.sync.aligned.m8n8.x4.trans.shared.b16 {%0,%1,%2,%3}, [%4];"
                 : "=r"(r[0]), "=r"(r[1]), "=r"(r[2]), "=r"(r[3]) : "r"(addr));
}
__device__ __forceinline__ void ldsm4(uint32_t (&r)[4], uint32_t addr) {
    asm volatile("ldmatrix.sync.aligned.m8n8.x4.shared.b16 {%0,%1,%2,%3}, [%4];"
                 : "=r"(r[0]), "=r"(r[1]), "=r"(r[2]), "=r"(r[3]) : "r"(addr));
}
__device__ __forceinline__ void mma16816(float (&c)[4], uint32_t a0, uint32_t a1, uint32_t a2, uint32_t a3,
                                         uint32_t b0, uint32_t b1) {
    asm("mma.sync.aligned.m16n8k16.row.col.f32.bf16.bf16.f32 {%0,%1,%2,%3}, {%4,%5,%6,%7}, {%8,%9}, {%0,%1,%2,%3};"
        : "+f"(c[0]), "+f"(c[1]), "+f"(c[2]), "+f"(c[3])
        : "r"(a0), "r"(a1), "r"(a2), "r"(a3), "r"(b0), "r"(b1));
}
__device__ __forceinline__ void ld_b128_if(uint4& v, const void* p, unsigned stale) {
    unsigned long long lo = v.x | ((unsigned long long)v.y << 32), hi = v.z | ((unsigned long long)v.w << 32);
    asm volatile("{\n.reg .pred p;\n.reg .b128 v;\nsetp.ne.u32 p, %3, 0;\nmov.b128 v, {%0, %1};\n"
                 "@p ld.relaxed.gpu.global.b128 v, [%2];\nmov.b128 {%0, %1}, v;\n}"
                 : "+l"(lo), "+l"(hi) : "l"(p), "r"(stale) : "memory");
    v = make_uint4((unsigned)lo, (unsigned)(lo >> 32), (unsigned)hi, (unsigned)(hi >> 32));
}
__device__ __forceinline__ void st_b128(void* p, uint4 v) {
    const unsigned long long lo = v.x | ((unsigned long long)v.y << 32), hi = v.z | ((unsigned long long)v.w << 32);
    asm volatile("{\n.reg .b128 v;\nmov.b128 v, {%1, %2};\nst.relaxed.gpu.global.b128 [%0], v;\n}"
                 ::"l"(p), "l"(lo), "l"(hi) : "memory");
}
__device__ __forceinline__ uint4 ld_2x64(const void* p) {
    unsigned long long lo, hi;
    asm volatile("ld.relaxed.gpu.global.v2.b64 {%0, %1}, [%2];" : "=l"(lo), "=l"(hi) : "l"(p) : "memory");
    return make_uint4((unsigned)lo, (unsigned)(lo >> 32), (unsigned)hi, (unsigned)(hi >> 32));
}
__device__ __forceinline__ void st_64(void* p, uint2 v) {
    const unsigned long long w = v.x | ((unsigned long long)v.y << 32);
    asm volatile("st.relaxed.gpu.global.b64 [%0], %1;" ::"l"(p), "l"(w) : "memory");
}
__device__ __forceinline__ unsigned ld_relaxed32(const unsigned* p) {
    unsigned v; asm volatile("ld.relaxed.gpu.global.u32 %0, [%1];" : "=r"(v) : "l"(p) : "memory"); return v;
}
__device__ __forceinline__ unsigned draw_ticket(unsigned* ticket) {
    unsigned v;
    asm volatile("{\n.reg .u32 l;\n.reg .u64 a;\nmov.u32 l, %%laneid;\nmad.wide.u32 a, l, 4, %1;\n"
                 "atom.relaxed.gpu.global.add.u32 %0, [a], 1;\n}" : "=r"(v) : "l"(ticket) : "memory");
    return v;
}
__device__ __forceinline__ uint32_t pack_bf16(float lo, float hi) {
    uint32_t r; asm("cvt.rn.bf16x2.f32 %0, %1, %2;" : "=r"(r) : "f"(hi), "f"(lo)); return r;
}
__device__ __forceinline__ float bf_lo(uint32_t v) { return __uint_as_float(v << 16); }
__device__ __forceinline__ float bf_hi(uint32_t v) { return __uint_as_float(v & 0xffff0000u); }
__device__ __forceinline__ float round_bf16(float v) { return __bfloat162float(__float2bfloat16_rn(v)); }
__device__ __forceinline__ float ex2(float v) { float r; asm("ex2.approx.ftz.f32 %0, %1;" : "=f"(r) : "f"(v)); return r; }
__device__ __forceinline__ float lg2(float v) { float r; asm("lg2.approx.ftz.f32 %0, %1;" : "=f"(r) : "f"(v)); return r; }

__global__ void __launch_bounds__(NTHREADS, 1)
fused_decode_kernel(const __nv_bfloat16* __restrict__ kc, const __nv_bfloat16* __restrict__ vc,
                    const __nv_bfloat16* __restrict__ x, const __nv_bfloat16* __restrict__ gate_w,
                    __nv_bfloat16* __restrict__ out, Scratch* scr,
                    const __grid_constant__ CUtensorMap tm_wq, const __grid_constant__ CUtensorMap tm_w1,
                    const __grid_constant__ CUtensorMap tm_w2, const __grid_constant__ CUtensorMap tm_wo) {
    extern __shared__ __align__(1024) unsigned char smem[];
    const uint32_t sb = (uint32_t)__cvta_generic_to_shared(smem);
    const int c = blockIdx.x;
    const bool role = c < NROLE;
    const uint32_t bars = sb + SM_BAR;
    const char* kbase = reinterpret_cast<const char*>(kc);
    const char* vbase = reinterpret_cast<const char*>(vc);
    uint64_t pol;
    asm volatile("createpolicy.fractional.L2::evict_first.b64 %0, 1.0;" : "=l"(pol));
    if (threadIdx.x == 0) {
        mbar_init(bars + BAR_K * 8, 1);
        mbar_init(bars + BAR_V * 8, 1);
        mbar_init(bars + BAR_WQ * 8, 1);
        mbar_init(bars + BAR_X * 8, 1);
        asm volatile("fence.proxy.async.shared::cta;" ::: "memory");
        mbar_expect_tx(bars + BAR_K * 8, TILE_BYTES);
        bulk_load_ef(sb + SM_KV, kbase + (size_t)c * TILE_BYTES, TILE_BYTES, bars + BAR_K * 8, pol);
        mbar_expect_tx(bars + BAR_V * 8, TILE_BYTES);
        bulk_load_ef(sb + SM_KV + TILE_BYTES, vbase + (size_t)c * TILE_BYTES, TILE_BYTES, bars + BAR_V * 8, pol);
        if (role) {
            mbar_expect_tx(bars + BAR_WQ * 8, 576 * 64);
#pragma unroll
            for (int i = 0; i < 3; i++) tma_load2d(sb + SM_WA + i * 192 * 64, &tm_wq, c * 32, i * 192, bars + BAR_WQ * 8);
            mbar_expect_tx(bars + BAR_X * 8, NB * DM * 2);
            asm volatile("cp.async.bulk.shared::cluster.global.mbarrier::complete_tx::bytes [%0], [%1], %2, [%3];"
                         ::"r"(sb + SM_X), "l"(x), "r"(NB * DM * 2), "r"(bars + BAR_X * 8) : "memory");
        }
    }
    __syncthreads();
    const int tid = (int)threadIdx.x - 32, warp = tid >> 5, lane = threadIdx.x & 31;
    const int g = lane >> 2, t = lane & 3;
    const int head = c >> 2, slice = c & 3;

    if (warp < 0) {
        unsigned tk = 0;
        uint32_t q0 = 0, q1 = 0, q2 = 0;
        auto gate = [&](uint32_t bar, uint32_t par) {
            if (q2) mbar_wait(q2 & ~1u, q2 & 1u);
            q2 = q1; q1 = q0; q0 = bar | par;
        };
        if (lane == 0) {
            tk = draw_ticket(scr->ticket);
#pragma unroll
            for (int i = 0; i < NBARS; i++)
                if (i != BAR_K && i != BAR_V && i != BAR_WQ && i != BAR_X) mbar_init(bars + i * 8, 1);
            asm volatile("fence.mbarrier_init.release.cluster;" ::: "memory");
        }
        __syncthreads();
        if (lane != 0) return;
        gate(bars + BAR_K * 8, 0);
        gate(bars + BAR_V * 8, 0);
        if (role) gate(bars + BAR_WQ * 8, 0);
        sts32(sb + SM_UNIT, c);
        mbar_arrive(bars + BAR_U * 8);
        unsigned cur = c + gridDim.x, k = 1;
        int phase = role ? 0 : 3;
        bool wfree = !role;
        while (true) {
            if (cur < (unsigned)NUNITS && !(k == W1_AT && phase == 0)) {
                const uint32_t st = k % NCONS, par = (k / NCONS) & 1;
                const uint32_t kbar = bars + (BAR_K + st) * 8, vbar = bars + (BAR_V + st) * 8;
                const uint32_t kbuf = sb + SM_KV + st * 2 * TILE_BYTES;
                gate(kbar, par);
                mbar_wait(bars + (BAR_E + st) * 8, par ^ 1);
                mbar_expect_tx(kbar, TILE_BYTES);
                bulk_load_ef(kbuf, kbase + (size_t)cur * TILE_BYTES, TILE_BYTES, kbar, pol);
                sts32(sb + SM_UNIT + st * 4, cur);
                mbar_arrive(bars + (BAR_U + st) * 8);
                if (k == 1) {
                    sts32(sb + SM_UNIT + 16, tk / NUNITS + 1);
                    mbar_arrive(bars + BAR_TAG * 8);
                }
                gate(vbar, par);
                mbar_expect_tx(vbar, TILE_BYTES);
                bulk_load_ef(kbuf + TILE_BYTES, vbase + (size_t)cur * TILE_BYTES, TILE_BYTES, vbar, pol);
                if (k != 1) tk = draw_ticket(scr->ticket);
                k++;
                if (k == 2 && role) asm volatile("prefetch.tensormap [%0];" ::"l"(&tm_w1) : "memory");
                if (k == 32 && role) {
                    mbar_wait(bars + BAR_WFREE * 8, 0);
                    asm volatile("fence.proxy.async.shared::cta;" ::: "memory");
                    asm volatile("prefetch.tensormap [%0];" ::"l"(&tm_w2) : "memory");
                    asm volatile("prefetch.tensormap [%0];" ::"l"(&tm_wo) : "memory");
                    wfree = true;
                }
                cur = (tk & (NUNITS - 1)) + 2 * gridDim.x;
                if (cur >= (unsigned)NUNITS) draw_ticket(scr->ticket);
                continue;
            }
            if (phase == 3) break;
            if (phase == 1 && !wfree) {
                mbar_wait(bars + BAR_WFREE * 8, 0);
                asm volatile("fence.proxy.async.shared::cta;" ::: "memory");
            }
            const CUtensorMap* tm = phase == 0 ? &tm_w1 : phase == 1 ? &tm_w2 : &tm_wo;
            const int rows = phase == 0 ? 192 : phase == 1 ? 48 : 64;
            const uint32_t bytes = phase == 0 ? 192 * 80 : rows * WROW;
            const int c0 = phase == 0 ? c * 36 - (c & 1) * 4 : slice * 144;
            int c1 = phase == 0 ? 0 : phase == 1 ? head * 144 : head * 128;
            uint32_t dst = sb + (phase == 2 ? SM_WA : SM_WB), bar = bars + (BAR_W1 + 3 * phase) * 8;
#pragma unroll 1
            for (int i = phase == 2 ? 1 : 0; i < 3; i++, dst += bytes, bar += 8, c1 += rows) {
                gate(bar, 0);
                mbar_expect_tx(bar, bytes);
                tma_load2d(dst, tm, c0, c1, bar);
            }
            phase++;
        }
#pragma unroll 1
        for (int i = 0; i < NCONS; i++, k++) {
            const uint32_t st = k % NCONS, par = (k / NCONS) & 1;
            mbar_wait(bars + (BAR_E + st) * 8, par ^ 1);
            sts32(sb + SM_UNIT + st * 4, 0xffffffffu);
            mbar_arrive(bars + (BAR_U + st) * 8);
        }
    } else if (warp < NCONS) {
        const uint32_t kbuf = sb + SM_KV + warp * 2 * TILE_BYTES, vbuf = kbuf + TILE_BYTES;
        const uint32_t kbar = bars + (BAR_K + warp) * 8, vbar = bars + (BAR_V + warp) * 8;
        const uint32_t par = g & 1;
        const uint32_t krow = kbuf + ((lane & 7) + 8 * ((lane >> 3) & 1)) * 256, kx16 = ((lane >> 4) ^ (lane & 7)) * 16;
        const uint32_t vrow = vbuf + ((lane & 7) + 8 * (lane >> 4)) * 256, vx16 = (((lane >> 3) & 1) ^ (lane & 7)) * 16;
        uint32_t ka[4], va[4];
#pragma unroll
        for (int j = 0; j < 4; j++) { ka[j] = krow + ((32 * j) ^ kx16); va[j] = vrow + ((32 * j) ^ vx16); }
        const uint32_t qx = (g >> 2) * 8 + ((g >> 1) & 1);
        const uint32_t pmask = t == (g >> 1) ? (par ? 0xffff0000u : 0x0000ffffu) : 0u;
        const float sc = 0.08838834764831845f * 1.4426950408889634f;
        __syncthreads();
        unsigned tag = 0;
        uint32_t live = 0;
        for (uint32_t ph = 1;; ph ^= 1) {
            asm volatile("" : "+r"(live));
            unsigned u = 0;
            uint32_t qb[8][2];
#pragma unroll
            for (int j = 0; j < 8; j++) qb[j][0] = qb[j][1] = 0;
            if (live) {
                mbar_wait(bars + (BAR_U + warp) * 8, ph);
                u = lds32(sb + SM_UNIT + warp * 4);
                if (u == 0xffffffffu) break;
                const uint4* qp = scr->q + (u / UNITS_PER_PAIR) * 32 + t * 2;
                uint4 qr[8];
                unsigned it = 0;
                while (true) {
#pragma unroll
                    for (int j = 0; j < 8; j++) qr[j] = ld_2x64(qp + (((j >> 1) * 8 + (j & 1)) ^ qx));
                    unsigned bad = 0;
#pragma unroll
                    for (int j = 0; j < 8; j++) bad |= (qr[j].y ^ tag) | (qr[j].w ^ tag);
                    if (!__any_sync(0xffffffffu, bad != 0)) break;
                    if (++it > SPIN_LIMIT) __trap();
                    __nanosleep(200);
                }
#pragma unroll
                for (int j = 0; j < 8; j++) { qb[j][0] = par ? qr[j].z : qr[j].x; qb[j][1] = par ? qr[j].x : qr[j].z; }
                mbar_wait(kbar, ph);
            }
            float sa[4][4];
#pragma unroll
            for (int kb = 0; kb < 4; kb++) { sa[kb][0] = sa[kb][1] = sa[kb][2] = sa[kb][3] = 0.f; }
#pragma unroll
            for (int j = 0; j < 8; j++) {
#pragma unroll
                for (int kb = 0; kb < 4; kb++) {
                    uint32_t a[4];
                    ldsm4(a, ka[j & 3] + (j >> 2) * 128 + kb * 4096);
                    mma16816(sa[kb], a[0], a[1], a[2], a[3], qb[j][0], qb[j][1]);
                }
            }
            float s[4][2];
#pragma unroll
            for (int kb = 0; kb < 4; kb++) { s[kb][0] = par ? sa[kb][1] : sa[kb][0]; s[kb][1] = par ? sa[kb][3] : sa[kb][2]; }
            float m = fmaxf(fmaxf(fmaxf(s[0][0], s[0][1]), fmaxf(s[1][0], s[1][1])),
                            fmaxf(fmaxf(s[2][0], s[2][1]), fmaxf(s[3][0], s[3][1])));
            m = fmaxf(m, __shfl_xor_sync(0xffffffffu, m, 4));
            m = fmaxf(m, __shfl_xor_sync(0xffffffffu, m, 9));
            m = fmaxf(m, __shfl_xor_sync(0xffffffffu, m, 18));
            float l = 0.f;
            uint32_t pb[4][2];
#pragma unroll
            for (int kb = 0; kb < 4; kb++) {
#pragma unroll
                for (int hh = 0; hh < 2; hh++) {
                    const float p = ex2((s[kb][hh] - m) * sc);
                    l += p;
                    pb[kb][hh] = pack_bf16(p, p) & pmask;
                    asm volatile("" : "+r"(pb[kb][hh]));
                }
            }
            l += __shfl_xor_sync(0xffffffffu, l, 4);
            l += __shfl_xor_sync(0xffffffffu, l, 9);
            l += __shfl_xor_sync(0xffffffffu, l, 18);
            float rl;
            asm("rcp.approx.ftz.f32 %0, %1;" : "=f"(rl) : "f"(l));
            rl = __shfl_sync(0xffffffffu, rl, 0);
            const float lse = __shfl_sync(0xffffffffu, fmaf(m, sc, lg2(l)), 0);
            if (live) mbar_wait(vbar, ph);
            float o[8][4];
#pragma unroll
            for (int j = 0; j < 8; j++) { o[j][0] = o[j][1] = o[j][2] = o[j][3] = 0.f; }
#pragma unroll
            for (int kb = 0; kb < 4; kb++) {
#pragma unroll
                for (int j = 0; j < 8; j++) {
                    uint32_t a[4];
                    ldsm4t(a, va[j & 3] + (j >> 2) * 128 + kb * 4096);
                    mma16816(o[j], a[0], a[1], a[2], a[3], pb[kb][0], pb[kb][1]);
                }
            }
            float e[8][2];
#pragma unroll
            for (int j = 0; j < 8; j++) { e[j][0] = o[j][0] + o[j][3]; e[j][1] = o[j][1] + o[j][2]; }
#pragma unroll
            for (int j = 0; j < 8; j += 2) {
                e[j][0] += __shfl_xor_sync(0xffffffffu, e[j + 1][0], 1);
                e[j][1] += __shfl_xor_sync(0xffffffffu, e[j + 1][1], 1);
            }
#pragma unroll
            for (int j = 0; j < 8; j += 4) {
                e[j][0] += __shfl_xor_sync(0xffffffffu, e[j + 2][0], 2);
                e[j][1] += __shfl_xor_sync(0xffffffffu, e[j + 2][1], 2);
            }
            const uint4 pv = make_uint4(pack_bf16(e[0][0] * rl, e[0][1] * rl), pack_bf16(e[4][0] * rl, e[4][1] * rl),
                                        __float_as_uint(lse), tag);
            if (live) {
                st_b128(&scr->part[(size_t)u * 32 + lane], pv);
                __syncwarp();
                if (lane == 0) mbar_arrive(bars + (BAR_E + warp) * 8);
            } else {
                asm volatile("" ::"r"(pv.x), "r"(pv.y), "r"(pv.z));
                mbar_wait(bars + BAR_TAG * 8, 0);
                tag = lds32(sb + SM_UNIT + 16);
                if (role) mbar_wait(bars + BAR_QOWN * 8, 0); else __nanosleep(3000);
                live = 1;
            }
        }
        if (role && (warp == 0 || (warp == 1 && head < 4))) {
            const int unit = warp * 32 + head;
            const uint4* src = &scr->xbuf[(slice * 32 + (lane >> 3) * 8) * 288 + unit * 8 + (lane & 7)];
            uint32_t* dst = reinterpret_cast<uint32_t*>(out + (2 * (unit & 3) + ((lane >> 3) & 1)) * DM + slice * 144 +
                                                        (unit >> 2) * 16 + (lane & 6) + 8 * (lane >> 4));
            asm volatile("" : "+l"(src), "+l"(dst));
            const unsigned t2 = tag & 3u;
            uint4 ya[8];
#pragma unroll
            for (int i = 0; i < 8; i++) ya[i] = make_uint4(t2 ^ 2u, 0, 0, 0);
            mbar_wait(bars + BAR_WO * 8, 0);
            for (unsigned it = 0;; it++) {
                unsigned bad = 0;
#pragma unroll
                for (int i = 0; i < 8; i++) ld_b128_if(ya[i], src + i * 288, (ya[i].x ^ t2) & 3u);
#pragma unroll
                for (int i = 0; i < 8; i++) bad |= ya[i].x ^ t2;
                const bool done = __all_sync(0xffffffffu, (bad & 3u) == 0u);
                if (done || it == 0) {
                    float v0 = 0.f, v1 = 0.f, v2 = 0.f, v3 = 0.f;
#pragma unroll
                    for (int i = 0; i < 8; i++) {
                        v0 += __uint_as_float(ya[i].x & ~3u); v1 += __uint_as_float(ya[i].y);
                        v2 += __uint_as_float(ya[i].z); v3 += __uint_as_float(ya[i].w);
                    }
                    const bool hi = lane & 16, od = lane & 8;
                    const float k0 = (hi ? v2 : v0) + __shfl_xor_sync(0xffffffffu, hi ? v0 : v2, 16);
                    const float k1 = (hi ? v3 : v1) + __shfl_xor_sync(0xffffffffu, hi ? v1 : v3, 16);
                    const float r = (od ? k1 : k0) + __shfl_xor_sync(0xffffffffu, od ? k0 : k1, 8);
                    const uint32_t rw = pack_bf16(r, __shfl_xor_sync(0xffffffffu, r, 1));
                    if (done && !(lane & 1))
                        asm volatile("st.global.u32 [%0], %1;" ::"l"(dst), "r"(rw) : "memory");
                }
                if (done) break;
                if (it > SPIN_LIMIT) __trap();
            }
        }
    } else {
        const int a = warp - NCONS, at = tid - NCONS * 32;
        __syncthreads();
        if (!role) return;
        unsigned tag = 0;
#pragma unroll 1
        for (uint32_t live = 0; live < 2; live++) {
            asm volatile("" : "+r"(live));
            if (a < 8) {
                uint32_t xq[9][2];
                if (live) mbar_wait(bars + BAR_X * 8, 0);
#pragma unroll
                for (int i = 0; i < 9; i++) {
                    xq[i][0] = lds32(sb + SM_X + g * (DM * 2) + (a >> 1) * 288 + i * 32 + t * 4);
                    xq[i][1] = lds32(sb + SM_X + g * (DM * 2) + (a >> 1) * 288 + i * 32 + t * 4 + 16);
                }
                if (live) mbar_wait(bars + BAR_WQ * 8, 0);
                float acc[4] = {0.f, 0.f, 0.f, 0.f}, acb[4] = {0.f, 0.f, 0.f, 0.f};
                const int mt = a & 1;
#pragma unroll
                for (int i = 0; i < 9; i++) {
                    const int row = (a >> 1) * 144 + i * 16 + (lane & 7) + 8 * (lane >> 4);
                    const int ch = mt * 2 + ((lane >> 3) & 1);
                    uint32_t w[4];
                    ldsm4t(w, sb + SM_WA + row * 64 + ((ch ^ ((row >> 1) & 3)) << 4));
                    if (i & 1) mma16816(acb, w[0], w[1], w[2], w[3], xq[i][0], xq[i][1]);
                    else mma16816(acc, w[0], w[1], w[2], w[3], xq[i][0], xq[i][1]);
                }
                *reinterpret_cast<float4*>(smem + SM_RED + (a * 32 + lane) * 16) =
                    make_float4(acc[0] + acb[0], acc[1] + acb[1], acc[2] + acb[2], acc[3] + acb[3]);
            }
            named_sync(1, 288);
            if (at < 128) {
                const int b = at >> 4, cp = at & 15;
                const int mt = cp >> 3, r = (2 * cp) & 15;
                const float* rp = reinterpret_cast<const float*>(smem + SM_RED) +
                                  (mt * 32 + (r & 7) * 4 + (b >> 1)) * 4 + (r >> 3) * 2 + (b & 1);
                const float v0 = rp[0] + rp[256] + rp[512] + rp[768];
                const float v1 = rp[16] + rp[272] + rp[528] + rp[784];
                const uint32_t qword = pack_bf16(v0, v1);
                if (live)
                    st_64(reinterpret_cast<uint2*>(scr->q + (b * NH + head) * 32) + slice * 16 + (cp & 3) * 4 + (cp >> 2), make_uint2(qword, tag));
                else asm volatile("" ::"r"(qword));
            }
            if (!live) {
                mbar_wait(bars + BAR_TAG * 8, 0);
                tag = lds32(sb + SM_UNIT + 16);
                named_sync(1, 288);
            }
        }
        if (at == 0) mbar_arrive(bars + BAR_QOWN * 8);

        {
            const int mt = a % 3, kt = a / 3;
            uint32_t xh[12][2];
            mbar_wait(bars + BAR_X * 8, 0);
#pragma unroll
            for (int i = 0; i < 12; i++) {
                xh[i][0] = lds32(sb + SM_X + g * (DM * 2) + kt * 384 + i * 32 + t * 4);
                xh[i][1] = lds32(sb + SM_X + g * (DM * 2) + kt * 384 + i * 32 + t * 4 + 16);
            }
            mbar_wait(bars + (BAR_W1 + 0) * 8, 0);
            mbar_wait(bars + (BAR_W1 + 1) * 8, 0);
            mbar_wait(bars + (BAR_W1 + 2) * 8, 0);
            float acc[4] = {0.f, 0.f, 0.f, 0.f};
#pragma unroll
            for (int i = 0; i < 12; i++) {
                const int row = kt * 192 + i * 16 + (lane & 7) + 8 * (lane >> 4);
                uint32_t w[4];
                ldsm4t(w, sb + SM_WB + row * 80 + (mt * 2 + ((lane >> 3) & 1)) * 16);
                mma16816(acc, w[0], w[1], w[2], w[3], xh[i][0], xh[i][1]);
            }
            named_sync(1, 288);
            *reinterpret_cast<float4*>(smem + SM_RED + (a * 32 + lane) * 16) = make_float4(acc[0], acc[1], acc[2], acc[3]);
            named_sync(1, 288);
            if (at == 287) mbar_arrive(bars + BAR_WFREE * 8);
            if (at < 144) {
                const int b = at / 18, cp = at - b * 18;
                const int sc2 = 2 * cp + (c & 1) * 4;
                const int m2 = sc2 >> 4, r = sc2 & 15;
                const float* rp = reinterpret_cast<const float*>(smem + SM_RED) +
                                  (m2 * 32 + (r & 7) * 4 + (b >> 1)) * 4 + (r >> 3) * 2 + (b & 1);
                const float v0 = round_bf16(rp[0] + rp[384] + rp[768]);
                const float v1 = round_bf16(rp[16] + rp[400] + rp[784]);
                st_64(scr->h + b * (FF / 2) + c * 18 + cp,
                      make_uint2(pack_bf16(v0 / (1.0f + __expf(-v0)), v1 / (1.0f + __expf(-v1))), tag));
            }
        }

        if (a == 8) {
            for (int b = 0; b < NB; b++) {
                float sum = 0.f;
#pragma unroll
                for (int i = 0; i < 9; i++) {
                    const uint32_t xv = __ldg(reinterpret_cast<const uint32_t*>(x + b * DM) + lane + i * 32);
                    const uint32_t gv = __ldg(reinterpret_cast<const uint32_t*>(gate_w) + lane + i * 32);
                    sum += round_bf16(bf_lo(xv) * bf_lo(gv)) + round_bf16(bf_hi(xv) * bf_hi(gv));
                }
#pragma unroll
                for (int o2 = 16; o2 > 0; o2 >>= 1) sum += __shfl_xor_sync(0xffffffffu, sum, o2);
                const float z = round_bf16(sum);
                const float gt = round_bf16(1.0f / (1.0f + __expf(-z)));
                if (lane == 0) {
                    reinterpret_cast<float*>(smem + SM_GATE)[b] = gt;
                    reinterpret_cast<float*>(smem + SM_GATE)[8 + b] = round_bf16(1.0f - gt);
                }
            }
            __nanosleep(4000);
            for (int i = lane; i < 288; i += 32) {
                const int b = i / 36, ch = i - b * 36;
                const uint2* src = scr->h + b * (FF / 2) + head * 72 + ch * 2;
                uint4 v;
                unsigned it = 0;
                while (true) {
                    v = ld_2x64(src);
                    if (v.y == tag && v.w == tag) break;
                    if (++it > SPIN_LIMIT) __trap();
                    __nanosleep(200);
                }
                *reinterpret_cast<uint2*>(smem + SM_H + b * WROW + ch * 8) = make_uint2(v.x, v.z);
            }
            __syncwarp();
        }

#pragma unroll 1
        for (uint32_t live = 0; live < 2; live++) {
            asm volatile("" : "+r"(live));
            uint4* ydst = &scr->xbuf[(slice * 32 + head) * 288 + (a * 4 + t) * 8 + g];
            asm volatile("" : "+l"(ydst));
            if (a == 8) {
                const float n0 = reinterpret_cast<const float*>(smem + SM_GATE)[8 + 2 * t];
                const float n1 = reinterpret_cast<const float*>(smem + SM_GATE)[9 + 2 * t];
                float fa[9][4];
#pragma unroll
                for (int m = 0; m < 9; m++) { fa[m][0] = fa[m][1] = fa[m][2] = fa[m][3] = 0.f; }
                const uint32_t wsel = sb + SM_WB + ((lane & 7) + 8 * (lane >> 4)) * WROW + ((lane >> 3) & 1) * 16;
#pragma unroll 1
                for (int i3 = 0; i3 < 3; i3++) {
                    uint32_t hb[3][2];
#pragma unroll
                    for (int i = 0; i < 3; i++) {
                        hb[i][0] = lds32(sb + SM_H + g * WROW + (i3 * 3 + i) * 32 + t * 4);
                        hb[i][1] = lds32(sb + SM_H + g * WROW + (i3 * 3 + i) * 32 + t * 4 + 16);
                    }
                    if (live) mbar_wait(bars + (BAR_W2 + i3) * 8, 0);
#pragma unroll
                    for (int i = 0; i < 3; i++) {
#pragma unroll
                        for (int m = 0; m < 9; m++) {
                            uint32_t w[4];
                            ldsm4t(w, wsel + (i3 * 3 + i) * 16 * WROW + m * 32);
                            mma16816(fa[m], w[0], w[1], w[2], w[3], hb[i][0], hb[i][1]);
                        }
                    }
                }
#pragma unroll
                for (int m = 0; m < 9; m++)
                    *reinterpret_cast<float4*>(smem + SM_F + (m * 32 + lane) * 16) =
                        make_float4(n0 * fa[m][0], n1 * fa[m][1], n0 * fa[m][2], n1 * fa[m][3]);
            } else {
#pragma unroll 1
                for (int b = live ? NB - 1 : 0; b < NB - 1 + (int)live; b++) {
                    const int pair = b * NH + head;
                    if (at == 0) {
                        const unsigned base = (tag - 1) * NUNITS;
                        const unsigned need = min((pair + 1) * UNITS_PER_PAIR + MERGE_LAG, NUNITS);
                        unsigned it = 0;
                        while (ld_relaxed32(scr->ticket) - base < need) {
                            __nanosleep(live ? 200 : 1000);
                            if (++it > SPIN_LIMIT) __trap();
                        }
                    }
                    named_sync(2, 256);
                    uint4 pv[8];
                    const uint4* pp = &scr->part[(size_t)(pair * UNITS_PER_PAIR + a * 8) * 32 + lane];
#pragma unroll
                    for (int i = 0; i < 8; i++) pv[i] = make_uint4(0, 0, 0, tag + 1);
                    unsigned it = 0;
                    while (true) {
#pragma unroll
                        for (int i = 0; i < 8; i++) ld_b128_if(pv[i], pp + i * 32, pv[i].w ^ tag);
                        unsigned bad = 0;
#pragma unroll
                        for (int i = 0; i < 8; i++) bad |= pv[i].w ^ tag;
                        if (bad == 0) break;
                        if (++it > SPIN_LIMIT) __trap();
                    }
                    __syncwarp();
                    float mw = __uint_as_float(pv[0].z);
#pragma unroll
                    for (int i = 1; i < 8; i++) mw = fmaxf(mw, __uint_as_float(pv[i].z));
                    float lw = 0.f, o0 = 0.f, o1 = 0.f, o2 = 0.f, o3 = 0.f;
#pragma unroll
                    for (int i = 0; i < 8; i++) {
                        const float w = ex2(__uint_as_float(pv[i].z) - mw);
                        lw += w;
                        o0 = fmaf(w, bf_lo(pv[i].x), o0); o1 = fmaf(w, bf_hi(pv[i].x), o1);
                        o2 = fmaf(w, bf_lo(pv[i].y), o2); o3 = fmaf(w, bf_hi(pv[i].y), o3);
                    }
                    *reinterpret_cast<float4*>(smem + SM_RED + (a * 32 + lane) * 16) = make_float4(o0, o1, o2, o3);
                    if (lane == 0) *reinterpret_cast<float2*>(smem + SM_ML + a * 8) = make_float2(mw, lw);
                    named_sync(2, 256);
                    if (at < 128) {
                        const int ln = at >> 2, i = at & 3;
                        const float2* ml = reinterpret_cast<const float2*>(smem + SM_ML);
                        float M = ml[0].x;
#pragma unroll
                        for (int w = 1; w < 8; w++) M = fmaxf(M, ml[w].x);
                        float L = 0.f, ov = 0.f;
#pragma unroll
                        for (int w = 0; w < 8; w++) {
                            const float sw = ex2(ml[w].x - M);
                            L = fmaf(sw, ml[w].y, L);
                            ov = fmaf(sw, reinterpret_cast<const float*>(smem + SM_RED)[(w * 32 + ln) * 4 + i], ov);
                        }
                        const int d = (i >> 1) * 64 + 16 * (ln & 3) + 8 * (i & 1) + (ln >> 2);
                        reinterpret_cast<__nv_bfloat16*>(smem + SM_O)[b * 136 + d] = __float2bfloat16_rn(__fdividef(ov, L));
                    }
                }
            }
            named_sync(1, 288);

            float aa[4] = {0.f, 0.f, 0.f, 0.f}, ab[4] = {0.f, 0.f, 0.f, 0.f};
            const uint32_t wsel = sb + SM_WA + ((lane & 7) + 8 * (lane >> 4)) * WROW + (2 * a + ((lane >> 3) & 1)) * 16;
            uint32_t ob[8][2];
#pragma unroll
            for (int i = 0; i < 8; i++) {
                ob[i][0] = lds32(sb + SM_O + g * 272 + i * 32 + t * 4);
                ob[i][1] = lds32(sb + SM_O + g * 272 + i * 32 + t * 4 + 16);
            }
            const float4 f = *reinterpret_cast<const float4*>(smem + SM_F + at * 16);
            const float g0 = reinterpret_cast<const float*>(smem + SM_GATE)[2 * t];
            const float g1 = reinterpret_cast<const float*>(smem + SM_GATE)[2 * t + 1];
#pragma unroll
            for (int i = 0; i < 8; i += 2) {
                if (i % 4 == 0 && live) mbar_spin(bars + (BAR_WO + i / 4) * 8, 0);
                uint32_t w[4], w2[4];
                ldsm4t(w, wsel + i * 16 * WROW);
                ldsm4t(w2, wsel + (i + 1) * 16 * WROW);
                mma16816(aa, w[0], w[1], w[2], w[3], ob[i][0], ob[i][1]);
                mma16816(ab, w2[0], w2[1], w2[2], w2[3], ob[i + 1][0], ob[i + 1][1]);
            }
            st_b128(ydst, make_uint4((__float_as_uint(fmaf(g0, aa[0] + ab[0], f.x)) & ~3u) | ((tag & 3u) ^ (live ? 0u : 2u)),
                                     __float_as_uint(fmaf(g1, aa[1] + ab[1], f.y)), __float_as_uint(fmaf(g0, aa[2] + ab[2], f.z)),
                                     __float_as_uint(fmaf(g1, aa[3] + ab[3], f.w))));
        }
    }
}

__device__ float g_fb[NB * (NH * DH * 2 + FF)];
__global__ void fb_in_proj(const __nv_bfloat16* x, const __nv_bfloat16* wq, const __nv_bfloat16* w1) {
    const int n = blockIdx.x * blockDim.x + threadIdx.x, b = blockIdx.y;
    const bool isq = n < NH * DH;
    const __nv_bfloat16* w = isq ? wq + n : w1 + (n - NH * DH);
    const int ld = isq ? NH * DH : FF;
    float s = 0.f;
    for (int k = 0; k < DM; k++) s = fmaf(__bfloat162float(x[b * DM + k]), __bfloat162float(w[(size_t)k * ld]), s);
    s = round_bf16(s);
    if (isq) g_fb[b * NH * DH + n] = s;
    else g_fb[2 * NB * NH * DH + b * FF + n - NH * DH] = round_bf16(s / (1.0f + __expf(-s)));
}
__global__ void fb_attn(const __nv_bfloat16* kc, const __nv_bfloat16* vc) {
    __shared__ float sc[SK], red[DH];
    const int p = blockIdx.x, t = threadIdx.x;
    float mx = -INFINITY;
    for (int j = t; j < SK; j += DH) {
        float s = 0.f;
        for (int d = 0; d < DH; d++) s = fmaf(g_fb[p * DH + d], __bfloat162float(kc[((size_t)p * SK + j) * DH + d]), s);
        sc[j] = s * 0.08838834764831845f;
        mx = fmaxf(mx, sc[j]);
    }
    red[t] = mx;
    __syncthreads();
    for (int i = 0; i < DH; i++) mx = fmaxf(mx, red[i]);
    for (int j = t; j < SK; j += DH) sc[j] = __expf(sc[j] - mx);
    __syncthreads();
    float l = 0.f, o = 0.f;
    for (int j = 0; j < SK; j++) { l += sc[j]; o = fmaf(sc[j], __bfloat162float(vc[((size_t)p * SK + j) * DH + t]), o); }
    g_fb[NB * NH * DH + p * DH + t] = round_bf16(o / l);
}
__global__ void fb_out_proj(const __nv_bfloat16* x, const __nv_bfloat16* gw, const __nv_bfloat16* wo,
                            const __nv_bfloat16* w2, __nv_bfloat16* out) {
    const int n = blockIdx.x * blockDim.x + threadIdx.x, b = blockIdx.y;
    float z = 0.f, a = 0.f, f = 0.f;
    for (int k = 0; k < DM; k++) z += round_bf16(__bfloat162float(x[b * DM + k]) * __bfloat162float(gw[k]));
    for (int k = 0; k < NH * DH; k++) a = fmaf(g_fb[(NB + b) * NH * DH + k], __bfloat162float(wo[(size_t)k * DM + n]), a);
    for (int k = 0; k < FF; k++) f = fmaf(g_fb[2 * NB * NH * DH + b * FF + k], __bfloat162float(w2[(size_t)k * DM + n]), f);
    const float gt = round_bf16(1.0f / (1.0f + __expf(-round_bf16(z))));
    out[b * DM + n] = __float2bfloat16_rn(gt * a + round_bf16(1.0f - gt) * f);
}

typedef CUresult (*EncodeTiledFn)(CUtensorMap*, CUtensorMapDataType, cuuint32_t, void*, const cuuint64_t*,
                                  const cuuint64_t*, const cuuint32_t*, const cuuint32_t*, CUtensorMapInterleave,
                                  CUtensorMapSwizzle, CUtensorMapL2promotion, CUtensorMapFloatOOBfill);

void make_map(EncodeTiledFn enc, CUtensorMap* tm, const void* base, int cols, int rows, int bc, int br,
              CUtensorMapSwizzle sw) {
    cuuint64_t dims[2] = {(cuuint64_t)cols, (cuuint64_t)rows};
    cuuint64_t strides[1] = {(cuuint64_t)cols * 2};
    cuuint32_t box[2] = {(cuuint32_t)bc, (cuuint32_t)br};
    cuuint32_t es[2] = {1, 1};
    enc(tm, CU_TENSOR_MAP_DATA_TYPE_BFLOAT16, 2, const_cast<void*>(base), dims, strides, box, es,
        CU_TENSOR_MAP_INTERLEAVE_NONE, sw, CU_TENSOR_MAP_L2_PROMOTION_L2_128B, CU_TENSOR_MAP_FLOAT_OOB_FILL_NONE);
}

}

extern "C" void kernel_launch(void* const* d_in, const int* in_sizes, int n_in, void* d_out, int out_size) {
    (void)in_sizes; (void)n_in; (void)out_size;
    static int grid = -1;
    static EncodeTiledFn enc = nullptr;
    static Scratch* scr = nullptr;
    if (grid < 0) {
        int dev = 0, sms = 0, per_sm = 0;
        cudaGetDevice(&dev);
        cudaDeviceGetAttribute(&sms, cudaDevAttrMultiProcessorCount, dev);
        cudaFuncSetAttribute(fused_decode_kernel, cudaFuncAttributeMaxDynamicSharedMemorySize, SM_TOTAL);
        cudaOccupancyMaxActiveBlocksPerMultiprocessor(&per_sm, fused_decode_kernel, NTHREADS, SM_TOTAL);
        void* fn = nullptr;
        cudaDriverEntryPointQueryResult qr;
        cudaGetDriverEntryPoint("cuTensorMapEncodeTiled", &fn, cudaEnableDefault, &qr);
        enc = (EncodeTiledFn)fn;
        cudaGetSymbolAddress((void**)&scr, g_scratch);
        grid = (sms >= NROLE && per_sm >= 1 && enc != nullptr) ? sms : 0;
    }
    const __nv_bfloat16* x = (const __nv_bfloat16*)d_in[0];
    const __nv_bfloat16* kc = (const __nv_bfloat16*)d_in[1];
    const __nv_bfloat16* vc = (const __nv_bfloat16*)d_in[2];
    const __nv_bfloat16* wq = (const __nv_bfloat16*)d_in[3];
    const __nv_bfloat16* wo = (const __nv_bfloat16*)d_in[4];
    const __nv_bfloat16* w1 = (const __nv_bfloat16*)d_in[6];
    const __nv_bfloat16* w2 = (const __nv_bfloat16*)d_in[7];
    const __nv_bfloat16* gw = (const __nv_bfloat16*)d_in[8];
    __nv_bfloat16* out = (__nv_bfloat16*)d_out;
    if (grid == 0) {
        fb_in_proj<<<dim3((NH * DH + FF) / 128, NB), 128>>>(x, wq, w1);
        fb_attn<<<NB * NH, DH>>>(kc, vc);
        fb_out_proj<<<dim3(DM / 64, NB), 64>>>(x, gw, wo, w2, out);
        return;
    }
    CUtensorMap tm_wq, tm_w1, tm_w2, tm_wo;
    make_map(enc, &tm_wq, wq, NH * DH, DM, 32, 192, CU_TENSOR_MAP_SWIZZLE_64B);
    make_map(enc, &tm_w1, w1, FF, DM, 40, 192, CU_TENSOR_MAP_SWIZZLE_NONE);
    make_map(enc, &tm_w2, w2, DM, FF, 152, 48, CU_TENSOR_MAP_SWIZZLE_NONE);
    make_map(enc, &tm_wo, wo, DM, NH * DH, 152, 64, CU_TENSOR_MAP_SWIZZLE_NONE);
    fused_decode_kernel<<<grid, NTHREADS, SM_TOTAL>>>(kc, vc, x, gw, out, scr, tm_wq, tm_w1, tm_w2, tm_wo);
}
```
